```python
import torch

def _softmax(x, axis=-1):
    return torch.softmax(x, dim=axis)
def _gelu(x):
    return torch.nn.functional.gelu(x, approximate="tanh")
def _silu(x):
    return torch.nn.functional.silu(x)
def _sigmoid(x):
    return torch.sigmoid(x)
def _layernorm(x, axis=-1, eps=1e-5):
    m = x.mean(dim=axis, keepdim=True)
    v = x.var(dim=axis, keepdim=True, unbiased=False)
    return (x - m) / torch.sqrt(v + eps)
def _scatter_add(tgt, idx, src, axis=0):
    return tgt.clone().index_add_(axis, idx, src)
def _segment_sum(src, seg, n):
    out = torch.zeros((n,) + src.shape[1:], dtype=src.dtype)
    return out.index_add_(0, seg, src)
def _pad(x, pw):
    flat = tuple(v for pair in reversed(pw) for v in pair)
    return torch.nn.functional.pad(x, flat)

kernel_name = 'parallel_sum__softmax_full_mha__mixer_channel_mlp__prompt'

def setup_inputs():

    _w = (lambda a: (lambda t: t.to(torch.bfloat16) if t.is_floating_point() else t)(torch.as_tensor(a)))
    def _A_setup():
        B, S, D = 1, 2048, 576
        return {
            "x": _w((lambda *s: torch.randn(*s, dtype=torch.bfloat16) * 0.05)(B, S, D)),
            "wqkv": _w((lambda *s: torch.randn(*s, dtype=torch.bfloat16) * 0.05)(D, 3 * D)),
            "wo": _w((lambda *s: torch.randn(*s, dtype=torch.bfloat16) * 0.05)(D, D)),
        }
    _A_in = _A_setup()

    def _B_setup():
        B, S, D, F = 1, 2048, 576, 4608
        return {
            "x": _w((lambda *s: torch.randn(*s, dtype=torch.bfloat16) * 0.05)(B, S, D)),
            "w1": _w((lambda *s: torch.randn(*s, dtype=torch.bfloat16) * 1.6)(D, F) * (D ** -0.5)),
            "b1": _w((lambda *s: torch.randn(*s, dtype=torch.bfloat16) * 0.8)(F)),
            "w2": _w((lambda *s: torch.randn(*s, dtype=torch.bfloat16) * 0.1)(F, D) * (F ** -0.5)),
            "b2": _w((lambda *s: torch.randn(*s, dtype=torch.bfloat16) * 0.1)(D)),
        }
    _B_in = _B_setup()

    return {
        "A_x": _A_in["x"],
        "A_wqkv": _A_in["wqkv"],
        "A_wo": _A_in["wo"],
        "B_x": _B_in["x"],
        "B_w1": _B_in["w1"],
        "B_b1": _B_in["b1"],
        "B_w2": _B_in["w2"],
        "B_b2": _B_in["b2"],
    }

def reference(A_x, A_wqkv, A_wo, B_x, B_w1, B_b1, B_w2, B_b2):
    def _A_ref(x, wqkv, wo):
        B, S, D = x.shape
        H = 32; Dh = D // H
        qkv = (lambda x, *d: x.permute(*d))((x @ wqkv).reshape(B, S, 3, H, Dh), 2, 0, 3, 1, 4)
        q, k, v = qkv[0], qkv[1], qkv[2]
        scale = Dh ** -0.5
        scores = torch.einsum("bhqd,bhkd->bhqk", q, k) * scale
        p = _softmax(scores, axis=-1)
        o = torch.einsum("bhqk,bhkd->bhqd", p, v)
        return (lambda x, *d: x.permute(*d))(o, 0, 2, 1, 3).reshape(B, S, D) @ wo

    def _B_ref(x, w1, b1, w2, b2):
        y = _layernorm(x, axis=-1)
        h = _gelu(torch.einsum("bsd,df->bsf", y, w1) + b1)
        return torch.einsum("bsf,fd->bsd", h, w2) + b2

    x = A_x
    xn = _layernorm(x, axis=-1)
    return x + _A_ref(xn, A_wqkv, A_wo) + _B_ref(xn, B_w1, B_b1, B_w2, B_b2)
```

```cpp
#include <cuda_runtime.h>
#include <cuda.h>
#include <cuda_bf16.h>
#include <stdint.h>

namespace {

constexpr int DM = 576;
constexpr int NTHREADS = 512;
constexpr uint32_t SLOT = 18432;
constexpr uint32_t OFF_XN = 0;
constexpr uint32_t OFF_B1 = 73728;
constexpr uint32_t OFF_ID = OFF_B1 + 4736;
constexpr uint32_t OFF_SL = 82944;
constexpr uint32_t OFF_H = OFF_SL + 6 * SLOT;
constexpr uint32_t OFF_BAR = OFF_SL + 8 * SLOT;
constexpr uint32_t OFF_S2 = OFF_BAR + 512;
constexpr uint32_t OFF_B2 = OFF_S2 + 256;
constexpr uint32_t SMEM_BYTES = OFF_B2 + 1280;
constexpr uint32_t SLICE = 98304;
constexpr uint32_t OFF_KN = 0;
constexpr uint32_t OFF_Q = 2048;
constexpr uint32_t OFF_KV = OFF_Q + 24576;
enum { B_QFULL = 0, B_QEMPTY = 8, B_STFREE2 = 16, B_QDONE = 17, B_STFREE = 18, B_PUB = 19, B_FULL = 20, B_FULLB = 26, B_EMPTY = 32,
       B_PEER = 38, B_RED = 39, B_HFULL = 40, B_HEMPTY = 42, B_E0 = 44, B_KV = 48, B_F0 = 58, B_COUNT = 64 };
constexpr int POLY_MASK = 0xB5B5;
constexpr int WAHEAD = 2;
constexpr int HSPLIT = 13;
constexpr int HSIG = 8;
constexpr float QSCALE = 0.23570226039551584f * 1.4426950408889634f;
constexpr float BOUND_MAX = 40.f;

__device__ __align__(1024) char g_QKV[96 * SLICE];
__device__ __align__(1024) char g_O[32 * 73728];
__device__ __align__(128) float4 g_part[64 * 384];
__device__ __align__(1024) char g_X[64 * 40960];
__device__ __align__(128) unsigned g_cnt[320];

template<int TB> __device__ __forceinline__ void wgmma_rs_n24(float (&d)[12], uint32_t a0, uint32_t a1, uint32_t a2, uint32_t a3, uint64_t db, int scale_d) {
  asm volatile("{\n.reg .pred p;\n"
    "setp.ne.b32 p, %17, 0;\n"
    "wgmma.mma_async.sync.aligned.m64n24k16.f32.bf16.bf16 {%0, %1, %2, %3, %4, %5, %6, %7, %8, %9, %10, %11}, {%12, %13, %14, %15}, %16, p, 1, 1, %18;\n}\n"
    : "+f"(d[0]), "+f"(d[1]), "+f"(d[2]), "+f"(d[3]), "+f"(d[4]), "+f"(d[5]), "+f"(d[6]), "+f"(d[7]), "+f"(d[8]), "+f"(d[9]), "+f"(d[10]), "+f"(d[11])
    : "r"(a0), "r"(a1), "r"(a2), "r"(a3), "l"(db), "r"(scale_d), "n"(TB));
}
template<int TB> __device__ __forceinline__ void wgmma_rs_n64(float (&d)[32], uint32_t a0, uint32_t a1, uint32_t a2, uint32_t a3, uint64_t db, int scale_d) {
  asm volatile("{\n.reg .pred p;\n"
    "setp.ne.b32 p, %37, 0;\n"
    "wgmma.mma_async.sync.aligned.m64n64k16.f32.bf16.bf16 {%0, %1, %2, %3, %4, %5, %6, %7, %8, %9, %10, %11, %12, %13, %14, %15, %16, %17, %18, %19, %20, %21, %22, %23, %24, %25, %26, %27, %28, %29, %30, %31}, {%32, %33, %34, %35}, %36, p, 1, 1, %38;\n}\n"
    : "+f"(d[0]), "+f"(d[1]), "+f"(d[2]), "+f"(d[3]), "+f"(d[4]), "+f"(d[5]), "+f"(d[6]), "+f"(d[7]), "+f"(d[8]), "+f"(d[9]), "+f"(d[10]), "+f"(d[11]), "+f"(d[12]), "+f"(d[13]), "+f"(d[14]), "+f"(d[15]), "+f"(d[16]), "+f"(d[17]), "+f"(d[18]), "+f"(d[19]), "+f"(d[20]), "+f"(d[21]), "+f"(d[22]), "+f"(d[23]), "+f"(d[24]), "+f"(d[25]), "+f"(d[26]), "+f"(d[27]), "+f"(d[28]), "+f"(d[29]), "+f"(d[30]), "+f"(d[31])
    : "r"(a0), "r"(a1), "r"(a2), "r"(a3), "l"(db), "r"(scale_d), "n"(TB));
}
template<int TB> __device__ __forceinline__ void wgmma_rs_n128(float (&d)[64], uint32_t a0, uint32_t a1, uint32_t a2, uint32_t a3, uint64_t db, int scale_d) {
  asm volatile("{\n.reg .pred p;\n"
    "setp.ne.b32 p, %69, 0;\n"
    "wgmma.mma_async.sync.aligned.m64n128k16.f32.bf16.bf16 {%0, %1, %2, %3, %4, %5, %6, %7, %8, %9, %10, %11, %12, %13, %14, %15, %16, %17, %18, %19, %20, %21, %22, %23, %24, %25, %26, %27, %28, %29, %30, %31, %32, %33, %34, %35, %36, %37, %38, %39, %40, %41, %42, %43, %44, %45, %46, %47, %48, %49, %50, %51, %52, %53, %54, %55, %56, %57, %58, %59, %60, %61, %62, %63}, {%64, %65, %66, %67}, %68, p, 1, 1, %70;\n}\n"
    : "+f"(d[0]), "+f"(d[1]), "+f"(d[2]), "+f"(d[3]), "+f"(d[4]), "+f"(d[5]), "+f"(d[6]), "+f"(d[7]), "+f"(d[8]), "+f"(d[9]), "+f"(d[10]), "+f"(d[11]), "+f"(d[12]), "+f"(d[13]), "+f"(d[14]), "+f"(d[15]), "+f"(d[16]), "+f"(d[17]), "+f"(d[18]), "+f"(d[19]), "+f"(d[20]), "+f"(d[21]), "+f"(d[22]), "+f"(d[23]), "+f"(d[24]), "+f"(d[25]), "+f"(d[26]), "+f"(d[27]), "+f"(d[28]), "+f"(d[29]), "+f"(d[30]), "+f"(d[31]), "+f"(d[32]), "+f"(d[33]), "+f"(d[34]), "+f"(d[35]), "+f"(d[36]), "+f"(d[37]), "+f"(d[38]), "+f"(d[39]), "+f"(d[40]), "+f"(d[41]), "+f"(d[42]), "+f"(d[43]), "+f"(d[44]), "+f"(d[45]), "+f"(d[46]), "+f"(d[47]), "+f"(d[48]), "+f"(d[49]), "+f"(d[50]), "+f"(d[51]), "+f"(d[52]), "+f"(d[53]), "+f"(d[54]), "+f"(d[55]), "+f"(d[56]), "+f"(d[57]), "+f"(d[58]), "+f"(d[59]), "+f"(d[60]), "+f"(d[61]), "+f"(d[62]), "+f"(d[63])
    : "r"(a0), "r"(a1), "r"(a2), "r"(a3), "l"(db), "r"(scale_d), "n"(TB));
}
template<int TB> __device__ __forceinline__ void wgmma_rs_n192(float (&d)[96], uint32_t a0, uint32_t a1, uint32_t a2, uint32_t a3, uint64_t db, int scale_d) {
  asm volatile("{\n.reg .pred p;\n"
    "setp.ne.b32 p, %101, 0;\n"
    "wgmma.mma_async.sync.aligned.m64n192k16.f32.bf16.bf16 {%0, %1, %2, %3, %4, %5, %6, %7, %8, %9, %10, %11, %12, %13, %14, %15, %16, %17, %18, %19, %20, %21, %22, %23, %24, %25, %26, %27, %28, %29, %30, %31, %32, %33, %34, %35, %36, %37, %38, %39, %40, %41, %42, %43, %44, %45, %46, %47, %48, %49, %50, %51, %52, %53, %54, %55, %56, %57, %58, %59, %60, %61, %62, %63, %64, %65, %66, %67, %68, %69, %70, %71, %72, %73, %74, %75, %76, %77, %78, %79, %80, %81, %82, %83, %84, %85, %86, %87, %88, %89, %90, %91, %92, %93, %94, %95}, {%96, %97, %98, %99}, %100, p, 1, 1, %102;\n}\n"
    : "+f"(d[0]), "+f"(d[1]), "+f"(d[2]), "+f"(d[3]), "+f"(d[4]), "+f"(d[5]), "+f"(d[6]), "+f"(d[7]), "+f"(d[8]), "+f"(d[9]), "+f"(d[10]), "+f"(d[11]), "+f"(d[12]), "+f"(d[13]), "+f"(d[14]), "+f"(d[15]), "+f"(d[16]), "+f"(d[17]), "+f"(d[18]), "+f"(d[19]), "+f"(d[20]), "+f"(d[21]), "+f"(d[22]), "+f"(d[23]), "+f"(d[24]), "+f"(d[25]), "+f"(d[26]), "+f"(d[27]), "+f"(d[28]), "+f"(d[29]), "+f"(d[30]), "+f"(d[31]), "+f"(d[32]), "+f"(d[33]), "+f"(d[34]), "+f"(d[35]), "+f"(d[36]), "+f"(d[37]), "+f"(d[38]), "+f"(d[39]), "+f"(d[40]), "+f"(d[41]), "+f"(d[42]), "+f"(d[43]), "+f"(d[44]), "+f"(d[45]), "+f"(d[46]), "+f"(d[47]), "+f"(d[48]), "+f"(d[49]), "+f"(d[50]), "+f"(d[51]), "+f"(d[52]), "+f"(d[53]), "+f"(d[54]), "+f"(d[55]), "+f"(d[56]), "+f"(d[57]), "+f"(d[58]), "+f"(d[59]), "+f"(d[60]), "+f"(d[61]), "+f"(d[62]), "+f"(d[63]), "+f"(d[64]), "+f"(d[65]), "+f"(d[66]), "+f"(d[67]), "+f"(d[68]), "+f"(d[69]), "+f"(d[70]), "+f"(d[71]), "+f"(d[72]), "+f"(d[73]), "+f"(d[74]), "+f"(d[75]), "+f"(d[76]), "+f"(d[77]), "+f"(d[78]), "+f"(d[79]), "+f"(d[80]), "+f"(d[81]), "+f"(d[82]), "+f"(d[83]), "+f"(d[84]), "+f"(d[85]), "+f"(d[86]), "+f"(d[87]), "+f"(d[88]), "+f"(d[89]), "+f"(d[90]), "+f"(d[91]), "+f"(d[92]), "+f"(d[93]), "+f"(d[94]), "+f"(d[95])
    : "r"(a0), "r"(a1), "r"(a2), "r"(a3), "l"(db), "r"(scale_d), "n"(TB));
}
template<int TA, int TB> __device__ __forceinline__ void wgmma_ss_n128(float (&d)[64], uint64_t da, uint64_t db, int scale_d) {
  asm volatile("{\n.reg .pred p;\n"
    "setp.ne.b32 p, %66, 0;\n"
    "wgmma.mma_async.sync.aligned.m64n128k16.f32.bf16.bf16 {%0, %1, %2, %3, %4, %5, %6, %7, %8, %9, %10, %11, %12, %13, %14, %15, %16, %17, %18, %19, %20, %21, %22, %23, %24, %25, %26, %27, %28, %29, %30, %31, %32, %33, %34, %35, %36, %37, %38, %39, %40, %41, %42, %43, %44, %45, %46, %47, %48, %49, %50, %51, %52, %53, %54, %55, %56, %57, %58, %59, %60, %61, %62, %63}, %64, %65, p, 1, 1, %67, %68;\n}\n"
    : "+f"(d[0]), "+f"(d[1]), "+f"(d[2]), "+f"(d[3]), "+f"(d[4]), "+f"(d[5]), "+f"(d[6]), "+f"(d[7]), "+f"(d[8]), "+f"(d[9]), "+f"(d[10]), "+f"(d[11]), "+f"(d[12]), "+f"(d[13]), "+f"(d[14]), "+f"(d[15]), "+f"(d[16]), "+f"(d[17]), "+f"(d[18]), "+f"(d[19]), "+f"(d[20]), "+f"(d[21]), "+f"(d[22]), "+f"(d[23]), "+f"(d[24]), "+f"(d[25]), "+f"(d[26]), "+f"(d[27]), "+f"(d[28]), "+f"(d[29]), "+f"(d[30]), "+f"(d[31]), "+f"(d[32]), "+f"(d[33]), "+f"(d[34]), "+f"(d[35]), "+f"(d[36]), "+f"(d[37]), "+f"(d[38]), "+f"(d[39]), "+f"(d[40]), "+f"(d[41]), "+f"(d[42]), "+f"(d[43]), "+f"(d[44]), "+f"(d[45]), "+f"(d[46]), "+f"(d[47]), "+f"(d[48]), "+f"(d[49]), "+f"(d[50]), "+f"(d[51]), "+f"(d[52]), "+f"(d[53]), "+f"(d[54]), "+f"(d[55]), "+f"(d[56]), "+f"(d[57]), "+f"(d[58]), "+f"(d[59]), "+f"(d[60]), "+f"(d[61]), "+f"(d[62]), "+f"(d[63])
    : "l"(da), "l"(db), "r"(scale_d), "n"(TA), "n"(TB));
}
template<int TA, int TB> __device__ __forceinline__ void wgmma_ss_n192(float (&d)[96], uint64_t da, uint64_t db, int scale_d) {
  asm volatile("{\n.reg .pred p;\n"
    "setp.ne.b32 p, %98, 0;\n"
    "wgmma.mma_async.sync.aligned.m64n192k16.f32.bf16.bf16 {%0, %1, %2, %3, %4, %5, %6, %7, %8, %9, %10, %11, %12, %13, %14, %15, %16, %17, %18, %19, %20, %21, %22, %23, %24, %25, %26, %27, %28, %29, %30, %31, %32, %33, %34, %35, %36, %37, %38, %39, %40, %41, %42, %43, %44, %45, %46, %47, %48, %49, %50, %51, %52, %53, %54, %55, %56, %57, %58, %59, %60, %61, %62, %63, %64, %65, %66, %67, %68, %69, %70, %71, %72, %73, %74, %75, %76, %77, %78, %79, %80, %81, %82, %83, %84, %85, %86, %87, %88, %89, %90, %91, %92, %93, %94, %95}, %96, %97, p, 1, 1, %99, %100;\n}\n"
    : "+f"(d[0]), "+f"(d[1]), "+f"(d[2]), "+f"(d[3]), "+f"(d[4]), "+f"(d[5]), "+f"(d[6]), "+f"(d[7]), "+f"(d[8]), "+f"(d[9]), "+f"(d[10]), "+f"(d[11]), "+f"(d[12]), "+f"(d[13]), "+f"(d[14]), "+f"(d[15]), "+f"(d[16]), "+f"(d[17]), "+f"(d[18]), "+f"(d[19]), "+f"(d[20]), "+f"(d[21]), "+f"(d[22]), "+f"(d[23]), "+f"(d[24]), "+f"(d[25]), "+f"(d[26]), "+f"(d[27]), "+f"(d[28]), "+f"(d[29]), "+f"(d[30]), "+f"(d[31]), "+f"(d[32]), "+f"(d[33]), "+f"(d[34]), "+f"(d[35]), "+f"(d[36]), "+f"(d[37]), "+f"(d[38]), "+f"(d[39]), "+f"(d[40]), "+f"(d[41]), "+f"(d[42]), "+f"(d[43]), "+f"(d[44]), "+f"(d[45]), "+f"(d[46]), "+f"(d[47]), "+f"(d[48]), "+f"(d[49]), "+f"(d[50]), "+f"(d[51]), "+f"(d[52]), "+f"(d[53]), "+f"(d[54]), "+f"(d[55]), "+f"(d[56]), "+f"(d[57]), "+f"(d[58]), "+f"(d[59]), "+f"(d[60]), "+f"(d[61]), "+f"(d[62]), "+f"(d[63]), "+f"(d[64]), "+f"(d[65]), "+f"(d[66]), "+f"(d[67]), "+f"(d[68]), "+f"(d[69]), "+f"(d[70]), "+f"(d[71]), "+f"(d[72]), "+f"(d[73]), "+f"(d[74]), "+f"(d[75]), "+f"(d[76]), "+f"(d[77]), "+f"(d[78]), "+f"(d[79]), "+f"(d[80]), "+f"(d[81]), "+f"(d[82]), "+f"(d[83]), "+f"(d[84]), "+f"(d[85]), "+f"(d[86]), "+f"(d[87]), "+f"(d[88]), "+f"(d[89]), "+f"(d[90]), "+f"(d[91]), "+f"(d[92]), "+f"(d[93]), "+f"(d[94]), "+f"(d[95])
    : "l"(da), "l"(db), "r"(scale_d), "n"(TA), "n"(TB));
}

__device__ __forceinline__ uint32_t smem_u32(const void* p) { return (uint32_t)__cvta_generic_to_shared(p); }
__device__ __forceinline__ uint64_t mkdesc(uint32_t addr, uint32_t lbo, uint32_t sbo, uint32_t swz) {
  return (uint64_t)((addr & 0x3FFFF) >> 4) | ((uint64_t)(lbo >> 4) << 16) | ((uint64_t)(sbo >> 4) << 32) | ((uint64_t)swz << 62);
}
__device__ __forceinline__ void wg_fence() { asm volatile("wgmma.fence.sync.aligned;" ::: "memory"); }
__device__ __forceinline__ void wg_commit() { asm volatile("wgmma.commit_group.sync.aligned;" ::: "memory"); }
template <int N> __device__ __forceinline__ void wg_wait() { asm volatile("wgmma.wait_group.sync.aligned %0;" ::"n"(N) : "memory"); }
template <int N> __device__ __forceinline__ void fence_regs(float (&r)[N]) {
#pragma unroll
  for (int i = 0; i < N; i++) asm volatile("" : "+f"(r[i])::"memory");
}
template <int N> __device__ __forceinline__ void def_regs(float (&r)[N]) {
#pragma unroll
  for (int i = 0; i < N; i++) asm volatile("" : "=f"(r[i]));
}
__device__ __forceinline__ void mbar_init(uint32_t bar, int cnt) { asm volatile("mbarrier.init.shared::cta.b64 [%0], %1;" ::"r"(bar), "r"(cnt)); }
__device__ __forceinline__ void mbar_expect_tx(uint32_t bar, uint32_t bytes) {
  asm volatile("mbarrier.arrive.expect_tx.shared::cta.b64 _, [%0], %1;" ::"r"(bar), "r"(bytes) : "memory");
}
__device__ __forceinline__ void mbar_arrive(uint32_t bar) { asm volatile("mbarrier.arrive.shared::cta.b64 _, [%0];" ::"r"(bar) : "memory"); }
__device__ __forceinline__ void rel(uint32_t cb, int idx, int lane) {
  if (lane < 2) asm volatile("mbarrier.arrive.shared::cluster.b64 _, [%0];" ::"r"(cb + idx * 8) : "memory");
}
__device__ __forceinline__ void rel2(uint32_t cb, int idx, int lane) {
  if (lane < 2) asm volatile("mbarrier.arrive.shared::cluster.b64 _, [%0], 2;" ::"r"(cb + idx * 8) : "memory");
}
__device__ __forceinline__ void mbar_wait(uint32_t bar, uint32_t parity) {
  asm volatile("{\n.reg .pred p;\n.reg .u32 n;\nmbarrier.try_wait.parity.shared::cta.b64 p, [%0], %1;\n@p bra WD;\nmov.u32 n, 0;\nWL:\n"
               "mbarrier.try_wait.parity.shared::cta.b64 p, [%0], %1;\n@p bra WD;\n"
               "add.u32 n, n, 1;\nsetp.lt.u32 p, n, 65536;\n@p bra WL;\nWD:\n}\n" ::"r"(bar), "r"(parity) : "memory");
}
__device__ __forceinline__ uint32_t mapa(uint32_t addr, uint32_t cta) { uint32_t r; asm("mapa.shared::cluster.u32 %0, %1, %2;" : "=r"(r) : "r"(addr), "r"(cta)); return r; }
__device__ __forceinline__ void tma3d(uint32_t dst, const CUtensorMap* tm, int c0, int c1, int c2, uint32_t bar) {
  asm volatile("cp.async.bulk.tensor.3d.shared::cluster.global.mbarrier::complete_tx::bytes [%0], [%1, {%3, %4, %5}], [%2];"
               ::"r"(dst), "l"(tm), "r"(bar), "r"(c0), "r"(c1), "r"(c2) : "memory");
}
__device__ __forceinline__ void bulk_g2s(uint32_t dst, const void* src, uint32_t bytes, uint32_t bar) {
  asm volatile("cp.async.bulk.shared::cluster.global.mbarrier::complete_tx::bytes [%0], [%1], %2, [%3];" ::"r"(dst), "l"(src), "r"(bytes), "r"(bar) : "memory");
}
__device__ __forceinline__ void tma2d(uint32_t dst, const CUtensorMap* tm, int c0, int c1, uint32_t bar) {
  asm volatile("cp.async.bulk.tensor.2d.shared::cluster.global.mbarrier::complete_tx::bytes [%0], [%1, {%3, %4}], [%2];"
               ::"r"(dst), "l"(tm), "r"(bar), "r"(c0), "r"(c1) : "memory");
}
__device__ __forceinline__ void tma3d_mc(uint32_t dst, const CUtensorMap* tm, int c0, int c1, int c2, uint32_t bar) {
  asm volatile("cp.async.bulk.tensor.3d.shared::cluster.global.mbarrier::complete_tx::bytes.multicast::cluster [%0], [%1, {%3, %4, %5}], [%2], %6;"
               ::"r"(dst), "l"(tm), "r"(bar), "r"(c0), "r"(c1), "r"(c2), "h"((uint16_t)3) : "memory");
}
__device__ __forceinline__ void tma3d_prefetch(const CUtensorMap* tm, int c0, int c1, int c2) {
  asm volatile("cp.async.bulk.prefetch.tensor.3d.L2.global [%0, {%1, %2, %3}];" ::"l"(tm), "r"(c0), "r"(c1), "r"(c2) : "memory");
}
__device__ __forceinline__ void prefetch_map(const CUtensorMap* tm) { asm volatile("prefetch.tensormap [%0];" ::"l"(tm) : "memory"); }
__device__ __forceinline__ void bulk_g2s_mc(uint32_t dst, const void* src, uint32_t bytes, uint32_t bar) {
  asm volatile("cp.async.bulk.shared::cluster.global.mbarrier::complete_tx::bytes.multicast::cluster [%0], [%1], %2, [%3], %4;"
               ::"r"(dst), "l"(src), "r"(bytes), "r"(bar), "h"((uint16_t)3) : "memory");
}
__device__ __forceinline__ void tma2d_store(const CUtensorMap* tm, uint32_t src, int c0, int c1) {
  asm volatile("cp.async.bulk.tensor.2d.global.shared::cta.bulk_group [%0, {%2, %3}], [%1];" ::"l"(tm), "r"(src), "r"(c0), "r"(c1) : "memory");
}
__device__ __forceinline__ void bulk_s2g(void* dst, uint32_t src, uint32_t bytes) {
  asm volatile("cp.async.bulk.global.shared::cta.bulk_group [%0], [%1], %2;" ::"l"(dst), "r"(src), "r"(bytes) : "memory");
}
__device__ __forceinline__ void l2_prefetch(const void* p, uint32_t bytes) {
  asm volatile("cp.async.bulk.prefetch.L2.global [%0], %1;" ::"l"(p), "r"(bytes) : "memory");
}
__device__ __forceinline__ void fence_async_smem() { asm volatile("fence.proxy.async.shared::cta;" ::: "memory"); }
__device__ __forceinline__ void fence_async_global() { asm volatile("fence.proxy.async.global;" ::: "memory"); }
__device__ __forceinline__ void bar_sync(int id, int n) { asm volatile("bar.sync %0, %1;" ::"r"(id), "r"(n) : "memory"); }
__device__ __forceinline__ void bar_arrive(int id, int n) { asm volatile("bar.arrive %0, %1;" ::"r"(id), "r"(n) : "memory"); }
__device__ __forceinline__ unsigned ld_acquire(const unsigned* p) { unsigned v; asm volatile("ld.acquire.gpu.global.u32 %0, [%1];" : "=r"(v) : "l"(p) : "memory"); return v; }
__device__ __forceinline__ void red_add(unsigned* p) { asm volatile("red.relaxed.gpu.global.add.u32 [%0], 1;" ::"l"(p) : "memory"); }
__device__ __forceinline__ void wait_count(const unsigned* p, unsigned target) {
  uint32_t n = 0;
  while (ld_acquire(p) < target && ++n < 20000) {}
}
__device__ __forceinline__ float ex2(float x) { float y; asm("ex2.approx.ftz.f32 %0, %1;" : "=f"(y) : "f"(x)); return y; }
__device__ __forceinline__ float sqrt_ap(float x) { float y; asm("sqrt.approx.ftz.f32 %0, %1;" : "=f"(y) : "f"(x)); return y; }
__device__ __forceinline__ float rcp_ap(float x) { float y; asm("rcp.approx.ftz.f32 %0, %1;" : "=f"(y) : "f"(x)); return y; }
__device__ __forceinline__ float tanh_ap(float x) { float y; asm("tanh.approx.f32 %0, %1;" : "=f"(y) : "f"(x)); return y; }
__device__ __forceinline__ uint32_t packbf(float lo, float hi) { uint32_t r; asm("cvt.rn.bf16x2.f32 %0, %1, %2;" : "=r"(r) : "f"(hi), "f"(lo)); return r; }
__device__ __forceinline__ float bf_lo(uint32_t w) { return __uint_as_float(w << 16); }
__device__ __forceinline__ float bf_hi(uint32_t w) { return __uint_as_float(w & 0xFFFF0000u); }
__device__ __forceinline__ float bf_round(float x) { return __bfloat162float(__float2bfloat16_rn(x)); }
__device__ __forceinline__ uint32_t hfma2bf(uint32_t a, uint32_t b, uint32_t c) { uint32_t r; asm("fma.rn.bf16x2 %0, %1, %2, %3;" : "=r"(r) : "r"(a), "r"(b), "r"(c)); return r; }
__device__ __forceinline__ uint32_t hsub2bf(uint32_t a, uint32_t b) { uint32_t r; asm("sub.rn.bf16x2 %0, %1, %2;" : "=r"(r) : "r"(a), "r"(b)); return r; }
__device__ __forceinline__ float sq2(uint32_t w, float a) { float l = bf_lo(w), h = bf_hi(w); return fmaf(h, h, fmaf(l, l, a)); }
__device__ __forceinline__ void stsm4(uint32_t addr, uint32_t a, uint32_t b, uint32_t c, uint32_t d) {
  asm volatile("stmatrix.sync.aligned.m8n8.x4.shared.b16 [%0], {%1,%2,%3,%4};" ::"r"(addr), "r"(a), "r"(b), "r"(c), "r"(d) : "memory");
}

__device__ __forceinline__ uint32_t exp2_pair_fma(float t0, float t1, uint32_t cM, uint32_t cE) {
  uint32_t u = __byte_perm(__float_as_uint(t0), __float_as_uint(t1), 0x6521);
  uint32_t m, e;
  asm("lop3.b32 %0, %1, %2, %3, 0xEA;" : "=r"(m) : "r"(u), "r"(0x007F007Fu), "r"(cM));
  asm("lop3.b32 %0, %1, %2, %3, 0xEA;" : "=r"(e) : "r"(u), "r"(0x7F807F80u), "r"(cE));
  return hfma2bf(u, m, e);
}

__device__ __forceinline__ float ln_row(uint32_t (&w)[36], bool twice) {
  float s0 = 0.f, s1 = 0.f, q0 = 0.f, q1 = 0.f;
#pragma unroll
  for (int t = 0; t < 36; t++) { const float a = bf_lo(w[t]), b = bf_hi(w[t]); s0 += a; s1 += b; q0 = fmaf(a, a, q0); q1 = fmaf(b, b, q1); }
  float s = s0 + s1, ss = q0 + q1;
#pragma unroll
  for (int o = 4; o; o >>= 1) { s += __shfl_xor_sync(0xffffffffu, s, o); ss += __shfl_xor_sync(0xffffffffu, ss, o); }
  const float mean = s * (1.f / DM);
  const float var = fmaxf(fmaf(-mean, mean, ss * (1.f / DM)), 0.f);
  const float den = bf_round(sqrt_ap(bf_round(bf_round(var) + 1e-5f)));
  float inv = rcp_ap(den);
  const float back = 2.f * bf_round(sqrt_ap(bf_round(bf_round(var * inv * inv) + 1e-5f)));
  if (twice) inv *= rcp_ap(back);
  const float ih = bf_round(inv);
  const float res = twice ? (bf_round(mean) - mean) * inv : 0.f;
  const uint32_t m2 = packbf(mean, mean), h2 = packbf(ih, ih), l2 = packbf(inv - ih, inv - ih), r2 = packbf(res, res);
#pragma unroll
  for (int t = 0; t < 36; t++) { const uint32_t d = hsub2bf(w[t], m2); w[t] = hfma2bf(d, h2, hfma2bf(d, l2, r2)); }
  return back;
}

template <int N> struct SS;
template <> struct SS<128> { static __device__ __forceinline__ void run(float (&d)[64], uint64_t a, uint64_t b, int sc) { wgmma_ss_n128<0, 1>(d, a, b, sc); } };
template <int N> struct ST;
template <> struct ST<128> { static __device__ __forceinline__ void run(float (&d)[64], uint64_t a, uint64_t b) { wgmma_ss_n128<1, 1>(d, a, b, 1); } };
template <> struct ST<192> { static __device__ __forceinline__ void run(float (&d)[96], uint64_t a, uint64_t b) { wgmma_ss_n192<1, 1>(d, a, b, 1); } };
template <int N> struct RS;
template <> struct RS<128> { static __device__ __forceinline__ void run(float (&d)[64], uint32_t a, uint64_t b) { wgmma_rs_n128<1>(d, a, a, 0u, 0u, b, 0); } };
template <> struct RS<192> { static __device__ __forceinline__ void run(float (&d)[96], uint32_t a, uint64_t b) { wgmma_rs_n192<1>(d, a, a, 0u, 0u, b, 0); } };
template <> struct SS<192> { static __device__ __forceinline__ void run(float (&d)[96], uint64_t a, uint64_t b, int sc) { wgmma_ss_n192<0, 1>(d, a, b, sc); } };

template <int N>
__device__ __forceinline__ void qkv_mma(uint32_t sb, char* st, const float* rs, uint32_t ring, uint32_t qslot, int COL0, int gc0, int s0, int s1, int warp, int lane) {
  float acc[N / 2];
  def_regs(acc);
  const uint32_t bars = sb + OFF_BAR, cb = mapa(bars, lane & 1);
  uint64_t da = mkdesc(sb + OFF_XN, 16, 1024, 1);
  const uint64_t db0 = mkdesc(ring + COL0 * 32, 2048, 1024, 1);
  const uint32_t qs4 = qslot >> 4;
#pragma unroll 1
  for (int kb = 0; kb < 9; kb++) {
    const uint32_t fb = bars + (B_QFULL + 4 - (kb & 1) * 4) * 8, eb = cb + (B_QEMPTY + 4 - (kb & 1) * 4) * 8, pb = cb + (B_QEMPTY + 3 + (kb & 1) * 4) * 8;
    const uint64_t db = db0 + ((kb & 1) ? 0 : 4 * qs4);
#pragma unroll
    for (int k = 0; k < 4; k++) {
      mbar_wait(fb + k * 8, (kb >> 1) & 1);
      wg_fence();
      SS<N>::run(acc, da + k * 2, db + k * qs4, (kb | k) != 0);
      wg_commit();
      wg_wait<1>();
      if ((kb | k) != 0) rel(k ? eb : pb, k ? k - 1 : 0, lane);
    }
    da += 512;
  }
  int off9[9];
  const int c0 = gc0 + COL0 + 2 * (lane & 3);
  {
    int d = c0 % 18;
    int o = (c0 / 18 - s0) * 3072 + warp * 768 + (lane >> 2) * 16;
#pragma unroll
    for (int b = 0; b < 9; b++) {
      off9[b] = o + (d >> 3) * 128 + (d & 7) * 2;
      asm volatile("" : "+r"(off9[b]));
      d += 8;
      if (d >= 18) { d -= 18; o += 3072; }
    }
  }
  wg_wait<0>();
  fence_regs(acc);
  if (lane == 0) mbar_arrive(bars + B_QDONE * 8);
  if (gc0 + COL0 < DM) {
    const float sc0 = rs[warp * 16 + (lane >> 2)], sc1 = rs[warp * 16 + (lane >> 2) + 8];
#pragma unroll
    for (int i = 0; i < N / 2; i++) acc[i] *= (i & 2) ? sc1 : sc0;
  }
  mbar_wait(bars + B_QDONE * 8, 0);
#pragma unroll
  for (int b = 0; b < N / 8; b++) {
    bool ok = true;
    if (N == 192 && b < 2) ok = c0 + b * 8 >= s0 * 18;
    if (N != 192 && b >= 8) ok = c0 + b * 8 < s1 * 18;
    char* p = st + off9[b % 9] + (b / 9) * 12288;
    if (ok) {
      *(uint32_t*)p = packbf(acc[4 * b], acc[4 * b + 1]);
      *(uint32_t*)(p + 384) = packbf(acc[4 * b + 2], acc[4 * b + 3]);
    }
  }
}

__device__ __forceinline__ void finish_slice(char* slice, int rt, int lane) {
  const bool f0 = (POLY_MASK >> ((rt & 1) * 8 + (lane >> 3))) & 1, f1 = (POLY_MASK >> ((rt & 1) * 8 + 4 + (lane >> 3))) & 1;
  const uint32_t w2c = 0x3F803F80u;
  char* p = slice + (lane >> 3) * 384 + (lane & 7) * 16;
  float n2[2];
  uint32_t kc[2];
#pragma unroll
  for (int h = 0; h < 2; h++) {
    const uint4 ka = *(const uint4*)(p + h * 1536), kb = *(const uint4*)(p + h * 1536 + 128);
    kc[h] = *(const uint32_t*)(p + h * 1536 + 256);
    n2[h] = sq2(ka.x, sq2(ka.y, sq2(ka.z, sq2(ka.w, sq2(kc[h], 0.f))))) + sq2(kb.x, sq2(kb.y, sq2(kb.z, sq2(kb.w, 0.f))));
  }
  const uint32_t mx = min((__reduce_max_sync(0xffffffffu, max(__float_as_uint(n2[0]), __float_as_uint(n2[1]))) >> 16) + 1, 0x7F7Fu);
  *(uint4*)(p + 256) = make_uint4(kc[0], f0 ? 0x3F803F80u : 0x3F80u, f0 ? w2c : 0u, mx);
  *(uint4*)(p + 1536 + 256) = make_uint4(kc[1], f1 ? 0x3F803F80u : 0x3F80u, f1 ? w2c : 0u, mx);
  fence_async_smem();
  __syncwarp();
}
__device__ __forceinline__ int kv_head(int rt, int o) { return ((((rt >> 1) - (o >> 1)) & 15) << 1) | (o & 1); }
__device__ __forceinline__ void store_kv(uint32_t sb, int rt, int isv, int o) {
  const int h = kv_head(rt, o);
  bulk_s2g(g_QKV + (size_t)(32 + 2 * h) * SLICE + (o >> 1) * 12288 + isv * 6144 + (rt & 1) * 3072, sb + OFF_SL + 8 * SLOT - SLICE + h * 3072, 3072);
  asm volatile("cp.async.bulk.commit_group;" ::: "memory");
}
__device__ __forceinline__ void signal_stores(unsigned* cnt) {
  asm volatile("cp.async.bulk.wait_group 0;" ::: "memory");
  fence_async_global();
  red_add(cnt);
}

__device__ __forceinline__ void load_q(uint32_t sb, int head, int tile, int wg, int t) {
  const uint32_t bar = sb + OFF_BAR + (B_FULLB + 4 * t + wg) * 8;
  mbar_expect_tx(bar, 3072);
  bulk_g2s(sb + OFF_Q + (t & 1) * 12288 + wg * 3072, g_QKV + (size_t)head * SLICE + tile * 3072, 3072, bar);
}
__device__ __forceinline__ void load_kv_quarter(uint32_t sb, int head, int i, int s) {
  const uint32_t bar = sb + OFF_BAR + (B_KV + s) * 8;
  mbar_expect_tx(bar, 49152);
  bulk_g2s(sb + OFF_KV + s * 49152, g_QKV + (size_t)(32 + 2 * head) * SLICE + i * 49152, 49152, bar);
}
__device__ __forceinline__ void load_kv(uint32_t sb, int head, int i) {
  bulk_g2s_mc(sb + OFF_KV + i * 12288, g_QKV + (size_t)(32 + 2 * head) * SLICE + i * 12288, 12288, sb + OFF_BAR + (B_KV + i) * 8);
}

__device__ __forceinline__ void store_o(const float (&o)[12], uint32_t buf, int tile, int head, int wg, int warp, int lane, bool live) {
  const float l0 = __shfl_sync(0xffffffffu, o[8], (lane & ~3) | 1), l1 = __shfl_sync(0xffffffffu, o[10], (lane & ~3) | 1);
  const float r0 = rcp_ap(l0), r1 = rcp_ap(l1);
  const uint32_t kr = (lane >> 4) * 8 + (lane & 7), ch = warp * 2 + ((lane >> 3) & 1);
  const uint32_t a = buf + kr * 128 + ((ch ^ ((head * 2 + kr) & 7)) << 4);
  asm volatile("stmatrix.sync.aligned.m8n8.x4.trans.shared.b16 [%0], {%1,%2,%3,%4};" ::"r"(a), "r"(packbf(o[0] * r0, o[1] * r0)),
               "r"(packbf(o[2] * r1, o[3] * r1)), "r"(packbf(o[4] * r0, o[5] * r0)), "r"(packbf(o[6] * r1, o[7] * r1)) : "memory");
  asm volatile("stmatrix.sync.aligned.m8n8.x2.trans.shared.b16 [%0], {%1,%2};" ::"r"(a + 2048), "r"(packbf(o[8] * r0, o[9] * r0)),
               "r"(packbf(o[10] * r1, o[11] * r1)) : "memory");
  fence_async_smem();
  if (warp != 0) bar_arrive(2 + wg, 128);
  else {
    bar_sync(2 + wg, 128);
    if (lane == 0 && live) {
      bulk_s2g(g_O + (size_t)tile * 73728 + head * 2304, buf, 2304);
      asm volatile("cp.async.bulk.commit_group;" ::: "memory");
    }
    __syncwarp();
  }
}
__device__ __forceinline__ void signal_o(int tile, int head) { signal_stores(&g_cnt[64 + tile * 4 + (head >> 3)]); }

__device__ __forceinline__ void attention_role(uint32_t sb, int wg, int warp, int lane, int head, int rank, bool helper, const char* smem,
                                               const CUtensorMap* tmN,
                                               uint32_t cM, uint32_t cE) {
  const int q = lane & 3;
  const uint32_t bars = sb + OFF_BAR;
  wg_fence();
  constexpr uint64_t K2OFF = 16ull - (8ull << 16);
  auto head_of = [&](int t) { return helper ? head + 2 * t + (wg >> 1) : head; };
  auto tile_of = [&](int t) { return helper ? (((head >> 3) + 3) & 3) * 8 + (wg & 1) * 4 : (((head >> 3) + t) & 3) * 8 + rank * 4 + wg; };
  const int kofs = helper ? (wg >> 1) * 8 : 0;
  bool ok = __shfl_sync(0xffffffffu, true, 0);
  const uint32_t bc = q == 1 ? packbf(-BOUND_MAX, 382.f) : q == 2 ? 0x3ecd3a2fu : 0u;
#pragma unroll 1
  for (int t = 0; t < 4; t++) {
    const bool shared = !helper && wg == 0 && t == 3;
    const int kc0 = shared ? HSPLIT : 0, kc1 = helper ? HSPLIT : 16;
    mbar_wait(bars + (B_FULLB + 4 * t + wg) * 8, 0);
    __syncwarp();
    const uint32_t* qa = (const uint32_t*)(smem + OFF_Q + (t & 1) * 12288 + wg * 3072 + warp * 768) + lane;
    const uint32_t a0 = qa[0], a1 = qa[96], a2 = qa[32], a3 = qa[128];
    const uint32_t b0 = q == 0 ? qa[64] : bc, b1 = q == 0 ? qa[160] : bc;
    float o[12];
#pragma unroll
    for (int i = 0; i < 12; i++) o[i] = 0.f;
    int kc = kc0;
#pragma unroll 1
    do {
      if (t > 0 && kc == (helper ? 4 : shared ? 15 : 2) && warp == 0) {
        if (lane == 0) {
          if (helper) asm volatile("red.release.gpu.global.add.u32 [%0], 4;" ::"l"(&g_cnt[192 + head_of(t - 1) * 2 + (wg & 1)]) : "memory");
          else if (ok) signal_o(tile_of(t - 1), head);
          if (t < 3) load_q(sb, head_of(t + 1), tile_of(t + 1), wg, t + 1);
        }
        __syncwarp();
      }
      if (helper) {
        const int g = t * 4 + (kc >> 2), qs = (wg >> 1) * 2;
        if (g > 0 && g < 15) {
          wg_wait<0>();
          bar_sync(8 + (wg >> 1), 256);
          if (g == 1 && (wg & 1) && warp == 1) { wait_count(&g_cnt[16], 1024); fence_async_global(); }
          if ((threadIdx.x & 255) == 160) load_kv_quarter(sb, head_of((g + 1) >> 2), (g + 1) & 3, qs + (~g & 1));
          __syncwarp();
        }
        mbar_wait(bars + (B_KV + qs + (g & 1)) * 8, (g >> 1) & 1);
      } else if (t == 0) {
        const int rt = (head & ~1) | rank;
        if (kc < 2) {
          if (lane == 0) {
            if (kc == 1) signal_stores(&g_cnt[16]);
            else { if (wg >= 2) signal_stores(&g_cnt[8]); store_kv(sb, rt, head & 1, 16 + wg * 4 + warp); }
          }
        } else if (kc < 8 && wg == 0 && warp == 1) {
          wait_count(&g_cnt[kc * 4], kc * 256);
          fence_async_global();
          if (lane == 0) {
#pragma unroll 1
            for (int i = 2 * kc + rank; i < 4 * kc; i += 2) load_kv(sb, head, i);
            if (kc == 4) {
              mbar_expect_tx(bars + (B_FULL + 4) * 8, 1536);
#pragma unroll 1
              for (int i = 0; i < 3; i++) tma2d(sb + OFF_KN + i * 512, tmN, 128, (i ? 31 + 2 * head + i : head) * 32, bars + (B_FULL + 4) * 8);
            }
          }
        }
        wg_fence();
#pragma unroll 1
        for (int i = kc; i < max(2 * kc, 1); i++) mbar_wait(bars + (B_KV + i) * 8, 0);
      }
      int run = helper ? min(4, HSPLIT - kc) : t == 0 ? max(kc, 1) : kc == 0 ? 2 : kc == 2 ? 14 : kc == 15 ? 1 : 15 - kc;
      const uint32_t kaddr = sb + OFF_KV + (helper ? (kc & 7) | kofs : kc) * 12288;
      uint64_t k1 = mkdesc(kaddr, 128, 384, 0), v = mkdesc(kaddr + 6144, 384, 128, 0);
      kc += run;
#pragma unroll 1
      do {
      {
        float s[2][32];
        uint32_t p[2][16];
        wg_fence();
        wgmma_rs_n64<0>(s[0], a0, a1, a2, a3, k1, 0);
        wgmma_rs_n64<0>(s[0], b0, b1, 0, 0, k1 + K2OFF, 1);
        wg_commit();
#pragma unroll
        for (int u = 0; u < 2; u++) {
          if (u == 0) wg_wait<0>(); else wg_wait<1>();
          fence_regs(s[u]);
#pragma unroll
          for (int b = 0; b < 8; b++) {
            if ((POLY_MASK >> (u * 8 + b)) & 1) {
              p[u][2 * b] = exp2_pair_fma(s[u][4 * b], s[u][4 * b + 1], cM, cE);
              p[u][2 * b + 1] = exp2_pair_fma(s[u][4 * b + 2], s[u][4 * b + 3], cM, cE);
            } else {
              p[u][2 * b] = packbf(ex2(s[u][4 * b]), ex2(s[u][4 * b + 1]));
              p[u][2 * b + 1] = packbf(ex2(s[u][4 * b + 2]), ex2(s[u][4 * b + 3]));
            }
          }
          wg_fence();
          if (u == 0) {
            wgmma_rs_n64<0>(s[1], a0, a1, a2, a3, k1 + 192, 0);
            wgmma_rs_n64<0>(s[1], b0, b1, 0, 0, k1 + 192 + K2OFF, 1);
            wg_commit();
          }
#pragma unroll
          for (int kk = 0; kk < 4; kk++) wgmma_rs_n24<1>(o, p[u][4 * kk], p[u][4 * kk + 1], p[u][4 * kk + 2], p[u][4 * kk + 3], v + u * 192 + kk * 48, 1);
          wg_commit();
        }
      }
      k1 += 768; v += 768;
      } while (--run > 0);
    } while (kc < kc1);
    if (t == 0 && !helper) {
      mbar_wait(bars + (B_FULL + 4) * 8, 0);
      const uint32_t* kn = (const uint32_t*)(smem + OFF_KN) + 3;
      const uint32_t qm = __reduce_max_sync(0xffffffffu, kn[lane * 4]), km = __reduce_max_sync(0xffffffffu, kn[128 + (lane >> 1) * 16 + (lane & 1) * 4]);
      ok = __shfl_sync(0xffffffffu, bf_lo(qm) * bf_lo(km) <= BOUND_MAX * BOUND_MAX * 0.96f, 0);
    }
    wg_wait<0>();
    fence_regs(o);
    if (helper) {
      const int slot = head_of(t) * 2 + (wg & 1);
      float4* dst = g_part + slot * 384 + warp * 32 + lane;
#pragma unroll
      for (int i = 0; i < 3; i++) dst[i * 128] = make_float4(o[4 * i], o[4 * i + 1], o[4 * i + 2], o[4 * i + 3]);
      __syncwarp();
      if (lane == 0 && t == 3) asm volatile("red.release.gpu.global.add.u32 [%0], 1;" ::"l"(&g_cnt[192 + slot]) : "memory");
      __syncwarp();
      continue;
    }
    if (shared) {
      wait_count(&g_cnt[192 + head * 2 + rank], 4);
      const float4* src = g_part + (head * 2 + rank) * 384 + warp * 32 + lane;
#pragma unroll
      for (int i = 0; i < 3; i++) { const float4 pv = __ldcg(src + i * 128); o[4 * i] += pv.x; o[4 * i + 1] += pv.y; o[4 * i + 2] += pv.z; o[4 * i + 3] += pv.w; }
    }
    store_o(o, sb + OFF_Q + (t & 1) * 12288 + wg * 3072, tile_of(t), head, wg, warp, lane, ok);
  }
  if (helper) return;
  if (warp == 0 && lane == 0 && ok) signal_o(tile_of(3), head);
  __syncwarp();
  if (ok) return;
#pragma unroll 1
  for (int t = 0; t < 4; t++) {
    const int tile = tile_of(t);
    const uint32_t* qa = (const uint32_t*)(g_QKV + (size_t)head * SLICE + tile * 3072 + warp * 768) + lane;
    const uint32_t a0 = __ldcg(qa), a1 = __ldcg(qa + 96), a2 = __ldcg(qa + 32), a3 = __ldcg(qa + 128);
    const uint32_t b0 = q == 0 ? __ldcg(qa + 64) : 0u, b1 = q == 0 ? __ldcg(qa + 160) : 0u;
    uint64_t k1 = mkdesc(sb + OFF_KV, 128, 384, 0), v = mkdesc(sb + OFF_KV + 6144, 384, 128, 0);
    float o[12];
#pragma unroll
    for (int i = 0; i < 12; i++) o[i] = 0.f;
    float m0 = -INFINITY, m1 = -INFINITY;
#pragma unroll 1
    for (int kb = 0; kb < 32; kb++) {
      float s[32];
      wg_fence();
      wgmma_rs_n64<0>(s, a0, a1, a2, a3, k1, 0);
      wgmma_rs_n64<0>(s, b0, b1, 0, 0, k1 + K2OFF, 1);
      wg_commit();
      wg_wait<0>();
      fence_regs(s);
      fence_regs(o);
      float t0 = m0, t1 = m1;
#pragma unroll
      for (int b = 0; b < 8; b++) { t0 = fmaxf(t0, fmaxf(s[4 * b], s[4 * b + 1])); t1 = fmaxf(t1, fmaxf(s[4 * b + 2], s[4 * b + 3])); }
      t0 = fmaxf(t0, __shfl_xor_sync(0xffffffffu, t0, 1)); t0 = fmaxf(t0, __shfl_xor_sync(0xffffffffu, t0, 2));
      t1 = fmaxf(t1, __shfl_xor_sync(0xffffffffu, t1, 1)); t1 = fmaxf(t1, __shfl_xor_sync(0xffffffffu, t1, 2));
      const float c0 = ex2(m0 - t0), c1 = ex2(m1 - t1);
      m0 = t0; m1 = t1;
#pragma unroll
      for (int b = 0; b < 3; b++) { o[4 * b] *= c0; o[4 * b + 1] *= c0; o[4 * b + 2] *= c1; o[4 * b + 3] *= c1; }
      uint32_t p[16];
#pragma unroll
      for (int b = 0; b < 8; b++) {
        p[2 * b] = packbf(ex2(s[4 * b] - m0), ex2(s[4 * b + 1] - m0));
        p[2 * b + 1] = packbf(ex2(s[4 * b + 2] - m1), ex2(s[4 * b + 3] - m1));
      }
      wg_fence();
#pragma unroll
      for (int kk = 0; kk < 4; kk++) wgmma_rs_n24<1>(o, p[4 * kk], p[4 * kk + 1], p[4 * kk + 2], p[4 * kk + 3], v + kk * 48, 1);
      wg_commit();
      wg_wait<0>();
      k1 += (kb & 1) ? 576 : 192; v += (kb & 1) ? 576 : 192;
    }
    fence_regs(o);
    store_o(o, sb + OFF_Q + (t & 1) * 12288 + wg * 3072, tile, head, wg, warp, lane, true);
    if (warp == 0 && lane == 0) signal_o(tile, head);
    __syncwarp();
  }
}

template <int NO, int NS>
__device__ __forceinline__ void tail_role(float (&own)[NO / 2], float (&send)[NS / 2], uint32_t sb, int wg, int warp, int lane,
                                          int rt, int rank, int atom, int satom, const CUtensorMap* tmOut) {
  const uint32_t bars = sb + OFF_BAR, cb = mapa(bars, lane & 1);
  const uint64_t db0 = mkdesc(sb + OFF_SL + (atom - rank * 5) * 6144, 6144, 1024, 1);
  const uint64_t do0 = mkdesc(sb + OFF_H, 1024, 1024, 1);
  const uint32_t soff = (satom - (rank ^ 1) * 5) * 8192 + warp * 2048, sbase = sb + OFF_XN + (5 - rank) * 8192 + soff;
  const uint32_t obase = sb + OFF_XN + (atom - rank * 5) * 8192 + warp * 2048;
  auto toff = [&](int b) { return (b >> 3) * 8192 + (lane & 15) * 128 + ((((b + (lane >> 4)) ^ lane) & 7) << 4); };
  auto add_tile = [&]() {
    const uint64_t di = mkdesc(sb + OFF_ID + 896, 896, 128, 0), dt = mkdesc(sb + OFF_XN + (atom - rank * 5) * 8192, 8192, 1024, 1);
    wg_fence();
#pragma unroll
    for (int kk = 0; kk < 4; kk++) SS<NO>::run(own, di - kk * 16, dt + kk * 128, 1);
    wg_commit();
  };
  mbar_wait(bars + B_QFULL * 8, 0);
  add_tile();
  fence_regs(send);
#pragma unroll
  for (int b = 0; b < NS / 8; b += 2)
    stsm4(sbase + toff(b), packbf(send[4 * b], send[4 * b + 1]), packbf(send[4 * b + 2], send[4 * b + 3]),
          packbf(send[4 * b + 4], send[4 * b + 5]), packbf(send[4 * b + 6], send[4 * b + 7]));
  fence_async_smem();
  __syncwarp();
  if (lane == 0) {
#pragma unroll 1
    for (int a = 0; a < NS / 64; a++) bulk_s2g(g_X + (size_t)(rt * 2 + (rank ^ 1)) * 40960 + soff + a * 8192, sbase + a * 8192, 2048);
    asm volatile("cp.async.bulk.commit_group;" ::: "memory");
  }
  __syncwarp();
#pragma unroll 1
  for (int k = 0; k < 4; k++) {
    if (k == 3) {
      mbar_wait(bars + B_RED * 8, 0);
      add_tile();
    }
    mbar_wait(bars + (B_KV + k) * 8, 0);
#pragma unroll
    for (int j = 0; j < 3; j++) {
      mbar_wait(bars + (B_KV + 4 + j) * 8, k & 1);
      wg_fence();
#pragma unroll
      for (int i = 0; i < 3; i++) ST<NO>::run(own, do0 + (k & 1) * (SLOT >> 4) + (j * 3 + i) * 128, db0 + ((j + 1) % 3) * (SLOT >> 3) + i * 128);
      wg_commit();
      if (j > 0) {
        wg_wait<1>();
        if (k < 3) rel(cb, B_KV + 6 + j, lane);
      }
    }
    if (k == 0) {
      if (lane == 0) {
        mbar_arrive(bars + B_PEER * 8);
        signal_stores(&g_cnt[256 + rt * 2 + (rank ^ 1)]);
      }
      __syncwarp();
    }
    wg_wait<0>();
    if (k < 3) rel(cb, B_KV + 9, lane);
    if (lane == 0) mbar_arrive(bars + (B_HEMPTY + (k & 1)) * 8);
  }
  fence_regs(own);
#pragma unroll
  for (int b = 0; b < NO / 8; b += 2)
    stsm4(obase + toff(b), packbf(own[4 * b], own[4 * b + 1]), packbf(own[4 * b + 2], own[4 * b + 3]),
          packbf(own[4 * b + 4], own[4 * b + 5]), packbf(own[4 * b + 6], own[4 * b + 7]));
  fence_async_smem();
  __syncwarp();
  if (lane == 0) {
#pragma unroll 1
    for (int a = 0; a < NO / 64; a++) tma2d_store(tmOut, obase + a * 8192, (atom + a) * 64, rt * 64 + warp * 16);
    asm volatile("cp.async.bulk.commit_group;\ncp.async.bulk.wait_group.read 0;" ::: "memory");
  }
}

template <int NA>
__device__ __forceinline__ void gemm2_role(uint32_t sb, int wg, int warp, int lane, int rt, int rank, int a0, int a1,
                                           const CUtensorMap* tmOut) {
  const uint32_t bars = sb + OFF_BAR, cb = mapa(bars, lane & 1);
  float acc0[NA / 2], acc1[64];
  def_regs(acc0);
  def_regs(acc1);
  const uint64_t db0 = mkdesc(sb + OFF_SL + a0 * 2048, 2048, 1024, 1);
  const int d01 = (a1 - a0) * 128;
  const uint64_t dh0 = mkdesc(sb + OFF_H, 16, 1024, 1);
  {
    const uint32_t half = (lane & 3) == 0 ? 0x3F00u : 0u;
    bar_sync(8, 384);
    wg_fence();
    RS<NA>::run(acc0, half, mkdesc(sb + OFF_B2 + a0 * 128, 0, 16, 0));
    RS<128>::run(acc1, half, mkdesc(sb + OFF_B2 + a1 * 128, 0, 16, 0));
    wg_commit();
    wg_wait<0>();
  }
#pragma unroll 1
  for (int c = 0; c < 18; c++) {
    mbar_wait(bars + (B_HFULL + (c & 1)) * 8, (c >> 1) & 1);
    const uint64_t da0 = dh0 + (c & 1) * (SLOT >> 4);
    const uint32_t h0 = c == 17 ? 0 : 3, h1 = 3 - h0;
    const uint32_t par = c == 17 ? 0x27u : (c & 1) ? 0xFCu : 0xC0u;
    const uint64_t dbh[2] = {db0 + h0 * (SLOT >> 4), db0 + h1 * (SLOT >> 4)};
    const uint32_t bh[2] = {bars + h0 * 8, bars + h1 * 8}, ch[2] = {cb + h0 * 8, cb + h1 * 8};
#pragma unroll
    for (int s = 0; s < 8; s++) {
      mbar_wait(bh[(s / 3) & 1] + (B_FULLB + s % 3) * 8, (par >> s) & 1);
      wg_fence();
      SS<NA>::run(acc0, da0 + (s >> 2) * 512 + (s & 3) * 2, dbh[(s / 3) & 1] + (s % 3) * (SLOT >> 4), 1);
      SS<128>::run(acc1, da0 + (s >> 2) * 512 + (s & 3) * 2, dbh[(s / 3) & 1] + (s % 3) * (SLOT >> 4) + d01, 1);
      wg_commit();
      if (s > 0) {
        wg_wait<1>();
        rel(ch[((s - 1) / 3) & 1], B_EMPTY + (s - 1) % 3, lane);
      }
    }
    wg_wait<0>();
    rel(ch[0], B_EMPTY + 1, lane);
    if (lane == 0) mbar_arrive(bars + (B_HEMPTY + (c & 1)) * 8);
  }
  fence_regs(acc0);
  fence_regs(acc1);
  if (NA == 128 || rank == 0) tail_role<NA, 128>(acc0, acc1, sb, wg, warp, lane, rt, rank, a0, a1, tmOut);
  else tail_role<128, NA>(acc1, acc0, sb, wg, warp, lane, rt, rank, a1, a0, tmOut);
}

__global__ void __cluster_dims__(2, 1, 1) __launch_bounds__(NTHREADS, 1)
fused_kernel(const __grid_constant__ CUtensorMap tmQ9, const __grid_constant__ CUtensorMap tmQ5, const __grid_constant__ CUtensorMap tmN, const __grid_constant__ CUtensorMap tmW1,
             const __grid_constant__ CUtensorMap tmW2, const __grid_constant__ CUtensorMap tmWo,
             const __grid_constant__ CUtensorMap tmOut, const __grid_constant__ CUtensorMap tmX,
             const __nv_bfloat16* __restrict__ x, const __nv_bfloat16* __restrict__ b1, const __nv_bfloat16* __restrict__ b2,
             const void* wqkv, uint32_t cM, uint32_t cE) {
  extern __shared__ __align__(1024) char smem[];
  const int tid = threadIdx.x, lane = tid & 31;
  const int wid = __shfl_sync(0xffffffffu, tid >> 5, 0);
  const int cl = blockIdx.x >> 1, crank = blockIdx.x & 1;
  const int rank = (cl >> 1) & 1;
  const bool helper = blockIdx.x >= 128;
  const int rt = helper ? 0 : (cl >> 2) * 2 + crank;
  uint32_t w[36];
  {
    const uint4* xr = (const uint4*)x + (size_t)(rt * 64 + (tid >> 3)) * 72 + (tid & 7);
#pragma unroll
    for (int t = 0; t < 9; t++)
      asm volatile("ld.global.nc.v4.u32 {%0,%1,%2,%3}, [%4];" : "=r"(w[4 * t]), "=r"(w[4 * t + 1]), "=r"(w[4 * t + 2]), "=r"(w[4 * t + 3]) : "l"(xr + t * 8));
  }
  const uint32_t sb = smem_u32(smem);
  const uint32_t bars = sb + OFF_BAR;
  const int wg = wid >> 2, warp = wid & 3;
  const bool is_mlp = !(cl & 1) && !helper;
  const int quarter = (is_mlp ? 0 : 2) + rank;
  const int qatom = (0x12090400 >> (8 * quarter)) & 255;
  const int qs0 = (0x40200F00 >> (8 * quarter)) & 255, qs1 = (0x6040200F >> (8 * quarter)) & 255;
  const uint32_t qslot = is_mlp ? 10240 : SLOT, qring = sb + OFF_SL + (is_mlp ? 65536 : 0);
  const uint32_t off_st = OFF_SL + 8 * SLOT - (qs1 - qs0) * 3072;
  const int f0 = rank * 2304;

  auto load_qkv = [&](int n) {
    const int s = (n + 4) & 7;
    mbar_expect_tx(bars + (B_QFULL + s) * 8, qslot);
    if (((n ^ (n >> 2)) & 1) == crank) tma3d_mc(qring + s * qslot, is_mlp ? &tmQ5 : &tmQ9, 0, n * 16, qatom, bars + (B_QFULL + s) * 8);
  };
  auto warm = [&](int p) {
    if (rt < 9) { if (p < 18) tma3d_prefetch(&tmW1, 0, rt * 64, (f0 >> 6) + p * 2); }
    else if (rt < 17) { if (p > 0 && p < 19) tma3d_prefetch(&tmW2, 0, f0 + (p - 1) * 128 + (rt - 9) * 16, 0); }
    else if (rt < 29 && p == 16) tma3d_prefetch(&tmWo, 0, (rt - 17) * 48, rank * 5);
  };
  auto finish = [&]() {
    unsigned prev;
    asm volatile("atom.relaxed.gpu.global.add.u32 %0, [%1], 1;" : "=r"(prev) : "l"(&g_cnt[32]) : "memory");
    if (prev == 131) {
      g_cnt[0] = 0; g_cnt[8] = 0; g_cnt[16] = 0; g_cnt[32] = 0;
#pragma unroll 4
      for (int i = 0; i < 64; i++) ((uint4*)(g_cnt + 64))[i] = make_uint4(0u, 0u, 0u, 0u);
    }
  };

  if (helper) {
    if (lane == 0 && wid < 8) {
#pragma unroll 1
      for (int i = 0; i < 8; i++) mbar_init(bars + wid * 64 + i * 8, 1);
      asm volatile("fence.mbarrier_init.release.cluster;" ::: "memory");
    }
    __syncthreads();
  } else {
  if (lane == 0) {
    if (wid < 8) {
      mbar_init(bars + (B_QFULL + ((wid + 4) & 7)) * 8, 1);
    } else if (wid < 15) {
      const uint32_t cnts = wid == 8 ? (is_mlp ? 0x88888888u : 0xCCCCCCCCu) : wid == 9 ? (is_mlp ? 0x4844u : 0x4464u) : (wid == 10 || !is_mlp) ? 0u
                            : wid == 11 ? 0x04888888u : wid == 12 ? 0x44444422u : wid == 13 ? 0x80000000u : 0x00000088u;
      const uint32_t b0 = bars + (wid - 7) * 64;
#pragma unroll 1
      for (int i = 0; i < 8; i++) {
        mbar_init(b0 + i * 8, max(((cnts >> (4 * i)) & 15) * 2, 1u));
        if (wid >= 13 && (!is_mlp || (wid == 13 && i < 4))) mbar_expect_tx(b0 + i * 8, is_mlp ? SLOT : 12288);
      }
      if (wid == 11 && is_mlp) mbar_expect_tx(bars + B_RED * 8, rank == 0 ? 40960 : 32768);
    } else {
      l2_prefetch((const char*)wqkv + 442368 + blockIdx.x * 12096, 12096);
      if (is_mlp) { prefetch_map(&tmW1); prefetch_map(&tmW2); } else prefetch_map(&tmN);
    }
    asm volatile("fence.mbarrier_init.release.cluster;" ::: "memory");
  }
  __syncwarp();
  asm volatile("barrier.cluster.arrive.relaxed.aligned;" ::: "memory");
  if (wid == 15) {
    asm volatile("barrier.cluster.wait.aligned;" ::: "memory");
    if (lane == 0) {
#pragma unroll 1
      for (int n = 0; n < 8; n++) load_qkv(n);
    }
    __syncwarp();
  }
  {
    const float s2 = ln_row(w, is_mlp) * QSCALE;
    const int r = tid >> 3;
    if ((tid & 7) == 0) *(float*)(smem + OFF_S2 + r * 4) = s2;
    char* p = smem + OFF_XN + r * 128 + (((tid ^ r) & 7) << 4);
#pragma unroll
    for (int t = 0; t < 9; t++) *(uint4*)(p + t * 8192) = make_uint4(w[4 * t], w[4 * t + 1], w[4 * t + 2], w[4 * t + 3]);
  }
  fence_async_smem();
  __syncthreads();
  if (wid != 15) asm volatile("barrier.cluster.wait.aligned;" ::: "memory");

  if (wg == 3) {
    if (lane == 0) {
      auto load_w1_first = [&]() {
        mbar_expect_tx(bars + (B_F0 + warp) * 8, 16384);
        if ((warp & 1) == crank) tma3d_mc(sb + OFF_SL + warp * SLOT, &tmW1, 0, warp * 64, f0 >> 6, bars + (B_F0 + warp) * 8);
      };
      if (is_mlp) {
        if (warp < 3) load_w1_first();
        else for (int i = 0; i <= WAHEAD; i++) warm(i);
      }
#pragma unroll 1
      for (int n = 8 + warp; n < 36; n += 4) {
        mbar_wait(bars + (B_QEMPTY + ((n + 4) & 7)) * 8, ((n >> 3) - 1) & 1);
        load_qkv(n);
      }
      if (is_mlp && warp == 3) { mbar_wait(bars + B_QEMPTY * 8, 1); load_w1_first(); }
    }
    __syncwarp();
  } else if (wg == 0 || !is_mlp) {
    qkv_mma<192>(sb, smem + off_st, (const float*)(smem + OFF_S2), qring, qslot, wg * 192, qatom * 64, qs0, qs1, warp, lane);
  } else if (wg == 1) {
    qkv_mma<128>(sb, smem + off_st, (const float*)(smem + OFF_S2), qring, qslot, 192, qatom * 64, qs0, qs1, warp, lane);
  } else {
#pragma unroll 1
    for (int i = tid - 256; i < 296; i += 128)
      *(uint4*)(smem + OFF_B1 + i * 16) = i < 288 ? __ldg((const uint4*)b1 + rank * 288 + i) : make_uint4(0u, 0u, 0u, 0u);
    if (tid - 256 < 80) *(uint4*)(smem + OFF_B2 + (tid - 256) * 16) = tid - 256 < 72 ? __ldg((const uint4*)b2 + (tid - 256)) : make_uint4(0u, 0u, 0u, 0u);
#pragma unroll 1
    for (int i = tid - 256; i < 176; i += 128) {
      const uint32_t v = (i >> 3 == 7 || i >> 3 == 15) ? 0x3F80u << ((i & 1) * 16) : 0u, ws = (i & 7) >> 1;
      *(uint4*)(smem + OFF_ID + i * 16) = make_uint4(ws == 0 ? v : 0u, ws == 1 ? v : 0u, ws == 2 ? v : 0u, ws == 3 ? v : 0u);
    }
    fence_async_smem();
    bar_sync(4, 128);
    bar_arrive(8, 384);
  }
  if (!is_mlp || wg < 2) {
    bar_sync(6, is_mlp ? 256 : 512);
#pragma unroll 1
    for (int o = wid; o < qs1 - qs0; o += is_mlp ? 8 : 16) {
      finish_slice(smem + off_st + (is_mlp ? o : kv_head(rt, o)) * 3072, rt, lane);
      if (lane == 0) {
        if (is_mlp) {
          bulk_s2g(g_QKV + (size_t)(qs0 + o) * SLICE + rt * 3072, sb + off_st + o * 3072, 3072);
          if (o < 8) asm volatile("cp.async.bulk.commit_group;" ::: "memory");
        } else if (o < 8) store_kv(sb, rt, rank, o);
      }
    }
    if (wid < 8) {
      if (lane == 0) {
        if (is_mlp) {
          asm volatile("cp.async.bulk.commit_group;\ncp.async.bulk.wait_group.read 1;" ::: "memory");
          rel(mapa(bars, 0), B_STFREE, 0);
          rel(mapa(bars, 1), B_STFREE, 0);
          asm volatile("cp.async.bulk.wait_group.read 0;" ::: "memory");
          mbar_arrive(bars + B_STFREE2 * 8);
        }
        asm volatile("cp.async.bulk.wait_group 0;" ::: "memory");
        fence_async_global();
        mbar_arrive(bars + B_PUB * 8);
      }
    } else {
      mbar_wait(bars + B_PUB * 8, 0);
      if (lane == 0) store_kv(sb, rt, rank, wid);
    }
    __syncwarp();
    if (tid == 224) {
      mbar_wait(bars + B_PUB * 8, 0);
      red_add(&g_cnt[0]);
    }
    __syncwarp();
  }
  }

  if (!is_mlp) {
    const int head = helper ? (blockIdx.x - 128) * 8 : cl >> 1;
    if (warp < 2 && lane == 0) {
      wait_count(&g_cnt[0], 128);
      fence_async_global();
      if (warp == 0) {
#pragma unroll 1
        for (int t = 0; t < 2; t++)
          load_q(sb, helper ? head + 2 * t + (wg >> 1) : head,
                 helper ? (((head >> 3) + 3) & 3) * 8 + (wg & 1) * 4 : (((head >> 3) + t) & 3) * 8 + crank * 4 + wg, wg, t);
      } else if (helper) {
        if (wg & 1) { wait_count(&g_cnt[8], 512); fence_async_global(); }
        load_kv_quarter(sb, head + (wg >> 1), wg & 1, wg);
      } else if (wg >= 2) load_kv(sb, head, crank + (wg & 1) * 2);
    }
    __syncwarp();
    attention_role(sb, wg, warp, lane, head, crank, helper, smem, &tmN, cM, cE);
    if (tid == 0) finish();
  } else if (wg == 3) {
    asm volatile("setmaxnreg.dec.sync.aligned.u32 24;");
    auto issue = [&](uint32_t full, uint32_t dst, const CUtensorMap* tm, int c1, int c2, uint32_t bytes, int turn) {
      if (lane == 0) { if (((turn ^ warp) & 1) == crank) tma3d_mc(dst, tm, 0, c1, c2, full); mbar_expect_tx(full, bytes); }
      __syncwarp();
    };
#pragma unroll 1
    for (int kb = 4 + warp; kb < 9; kb += 4) {
      mbar_wait(bars + (B_E0 + warp) * 8, kb >> 3);
      issue(bars + (B_F0 + warp) * 8, sb + OFF_SL + warp * SLOT, &tmW1, kb * 64, f0 >> 6, 16384, 0);
    }
    if (warp < 3) {
      const uint32_t bw = bars + warp * 8, dw = sb + OFF_SL + warp * SLOT;
      uint32_t par0 = 1, par1 = 1;
      auto put = [&](int hi, const CUtensorMap* tm, int c1, int c2, uint32_t bytes, int fb) {
        uint32_t& par = hi ? par1 : par0;
        mbar_wait(bw + (B_EMPTY + 3 * hi) * 8, par);
        par ^= 1;
        issue(bw + (fb + 3 * hi) * 8, dw + 3 * hi * SLOT, tm, c1, c2, bytes, hi);
      };
      mbar_wait(bars + B_STFREE * 8, 0);
      mbar_wait(bars + (B_E0 + warp) * 8, warp > 0);
#pragma unroll 1
      for (int p = 1; p < 18; p++) {
        const int k2 = f0 + (p - 1) * 128 + warp * 16, a1 = (f0 >> 6) + p * 2;
        if (warp == 2 && lane == 0) warm(p + WAHEAD);
        __syncwarp();
        put(0, &tmW1, warp * 64, a1, 16384, B_FULL);
        put(1, &tmW1, warp * 64 + 192, a1, 16384, B_FULL);
        put(0, &tmW1, warp * 64 + 384, a1, 16384, B_FULL);
        put(1, &tmW2, k2, 0, SLOT, B_FULLB);
        put(0, &tmW2, k2 + 48, 0, SLOT, B_FULLB);
        if (warp < 2) put(1, &tmW2, k2 + 96, 0, SLOT, B_FULLB);
      }
      {
        const int k2 = f0 + 17 * 128 + warp * 16;
        put(0, &tmW2, k2, 0, SLOT, B_FULLB);
        put(1, &tmW2, k2 + 48, 0, SLOT, B_FULLB);
        if (warp < 2) put(0, &tmW2, k2 + 96, 0, SLOT, B_FULLB);
      }
      const uint32_t ds = (warp + 1) % 3;
      if (warp == 2) mbar_wait(bars + (B_EMPTY + 5) * 8, 0);
      mbar_wait(bars + (B_EMPTY + 2 * ds) * 8, (0x1Cu >> (2 * ds)) & 1);
      mbar_wait(bars + (B_EMPTY + 2 * ds + 1) * 8, (0x1Cu >> (2 * ds + 1)) & 1);
#pragma unroll 1
      for (int k = 0; k < 4; k++) {
        mbar_wait(bw + (B_KV + 7) * 8, ~k & 1);
        issue(bw + (B_KV + 4) * 8, sb + OFF_SL + ds * 2 * SLOT, &tmWo, (((rt >> 3) - k) & 3) * 144 + warp * 48, rank * 5, 30720, k);
      }
    } else if (lane == 0) {
#pragma unroll 1
      for (int i = 0; i < 8; i++) mbar_wait(bars + B_HEMPTY * 8, i & 1);
      prefetch_map(&tmWo); prefetch_map(&tmX); prefetch_map(&tmOut);
#pragma unroll 1
      for (int k = 0; k < 4; k++) {
        const int grp = ((rt >> 3) - k) & 3;
        mbar_wait(bars + (B_HEMPTY + (k & 1)) * 8, k >> 1);
        wait_count(&g_cnt[64 + rt * 4 + grp], 8);
        fence_async_global();
        bulk_g2s(sb + OFF_H + (k & 1) * SLOT, g_O + (size_t)rt * 73728 + grp * SLOT, SLOT, bars + (B_KV + k) * 8);
      }
      mbar_wait(bars + B_RED * 8, 0);
      finish();
    }
  } else if (wg == 2) {
    asm volatile("setmaxnreg.dec.sync.aligned.u32 104;");
    const uint64_t da0 = mkdesc(sb + OFF_XN, 16, 1024, 1);
    const uint64_t db0 = mkdesc(sb + OFF_SL, 8192, 1024, 1);
    const int hr = warp * 16 + (lane & 15);
    const uint32_t hrow = sb + OFF_H + hr * 128;
    const uint32_t ba = (lane & 3) == 0 ? 0x3F00u : 0u;
    const uint64_t dbias = mkdesc(sb + OFF_B1, 0, 16, 0);
    const uint32_t cb = mapa(bars, lane & 1);
#pragma unroll 1
    for (int c = 0; c < 18; c++) {
      float acc[64];
      wg_fence();
      wgmma_rs_n128<1>(acc, ba, ba, 0u, 0u, dbias + c * 16, 0);
      if (c == 0) {
#pragma unroll 1
        for (int kb = 0; kb < 9; kb++) {
          mbar_wait(bars + (B_F0 + (kb & 3)) * 8, (kb >> 2) & 1);
          wg_fence();
#pragma unroll
          for (int k = 0; k < 4; k++) wgmma_ss_n128<0, 1>(acc, da0 + kb * 512 + k * 2, db0 + (kb & 3) * (SLOT >> 4) + k * 128, 1);
          wg_commit();
          wg_wait<0>();
          rel(cb, B_E0 + (kb & 3), lane);
        }
      } else {
#pragma unroll
        for (int kb = 0; kb < 9; kb++) {
          mbar_wait(bars + (B_FULL + kb % 6) * 8, (kb >= 3 && kb < 6) ? (~c & 1) : kb / 6);
          wg_fence();
#pragma unroll
          for (int k = 0; k < 4; k++) wgmma_ss_n128<0, 1>(acc, da0 + kb * 512 + k * 2, db0 + (kb % 6) * (SLOT >> 4) + k * 128, 1);
          wg_commit();
          if (kb == HSIG && lane == 0) mbar_arrive(bars + (B_HFULL + ((c - 1) & 1)) * 8);
          if (kb > 0) {
            wg_wait<1>();
            rel2(cb, B_EMPTY + (kb - 1) % 6, lane);
          }
        }
      }
      wg_wait<0>();
      fence_regs(acc);
      if (c > 0) rel2(cb, B_EMPTY + 8 % 6, lane);
      if (c == 17) {
        bar_sync(4, 128);
        if (tid == 256) {
          mbar_expect_tx(bars + B_QFULL * 8, 40960);
          tma3d(sb + OFF_XN, &tmX, 0, rt * 64, rank * 5, bars + B_QFULL * 8);
        }
        __syncwarp();
      }
      if (c == 0) mbar_wait(bars + B_STFREE2 * 8, 0);
      else if (c >= 2) mbar_wait(bars + (B_HEMPTY + (c & 1)) * 8, ((c >> 1) - 1) & 1);
      const uint32_t hb = hrow + (c & 1) * SLOT;
#pragma unroll
      for (int b = 0; b < 16; b += 2) {
        uint32_t pk[4];
#pragma unroll
        for (int j = 0; j < 4; j++) {
          const float x0 = acc[4 * b + 2 * j], x1 = acc[4 * b + 2 * j + 1];
          constexpr float k1 = 2.f * 0.7978845608028654f, k2 = 8.f * 0.035677408136300125f;
          const float u0 = x0 * fmaf(x0 * x0, k2, k1), u1 = x1 * fmaf(x1 * x1, k2, k1);
          pk[j] = packbf(fmaf(x0, tanh_ap(u0), x0), fmaf(x1, tanh_ap(u1), x1));
        }
        const uint32_t cc = (b + (lane >> 4)) & 7;
        stsm4(hb + (b >> 3) * 8192 + ((cc ^ (hr & 7)) << 4), pk[0], pk[1], pk[2], pk[3]);
      }
      fence_async_smem();
      __syncwarp();
      if (c == 17 && lane == 0) mbar_arrive(bars + (B_HFULL + 1) * 8);
    }
    if (tid == 256) {
      mbar_wait(bars + B_PEER * 8, 0);
      wait_count(&g_cnt[256 + rt * 2 + rank], 8);
      fence_async_global();
      bulk_g2s(sb + OFF_XN, g_X + (size_t)(rt * 2 + rank) * 40960, rank == 0 ? 40960 : 32768, bars + B_RED * 8);
    }
  } else if (wg == 0) {
    asm volatile("setmaxnreg.inc.sync.aligned.u32 208;");
    gemm2_role<192>(sb, wg, warp, lane, rt, rank, 0, 5, &tmOut);
  } else {
    asm volatile("setmaxnreg.inc.sync.aligned.u32 176;");
    gemm2_role<128>(sb, wg, warp, lane, rt, rank, rank ? 7 : 3, rank ? 3 : 7, &tmOut);
  }
}

typedef CUresult (*EncodeFn)(CUtensorMap*, CUtensorMapDataType, cuuint32_t, void*, const cuuint64_t*, const cuuint64_t*, const cuuint32_t*,
                             const cuuint32_t*, CUtensorMapInterleave, CUtensorMapSwizzle, CUtensorMapL2promotion, CUtensorMapFloatOOBfill);

void make_map(EncodeFn fn, CUtensorMap* tm, const void* ptr, int rank, const cuuint64_t* dims, const cuuint64_t* strides, const cuuint32_t* box,
              CUtensorMapSwizzle swz) {
  cuuint32_t es[3] = {1, 1, 1};
  fn(tm, CU_TENSOR_MAP_DATA_TYPE_BFLOAT16, rank, const_cast<void*>(ptr), dims, strides, box, es, CU_TENSOR_MAP_INTERLEAVE_NONE, swz,
     CU_TENSOR_MAP_L2_PROMOTION_L2_256B, CU_TENSOR_MAP_FLOAT_OOB_FILL_NONE);
}

}

extern "C" void kernel_launch(void* const* d_in, const int* in_sizes, int n_in, void* d_out, int out_size) {
  const __nv_bfloat16* x = (const __nv_bfloat16*)d_in[0];
  const void* wqkv = d_in[1];
  const void* wo = d_in[2];
  const void* w1 = d_in[4];
  const __nv_bfloat16* b1 = (const __nv_bfloat16*)d_in[5];
  const void* w2 = d_in[6];
  const __nv_bfloat16* b2 = (const __nv_bfloat16*)d_in[7];

  void* fnp = nullptr;
  cudaDriverEntryPointQueryResult qr;
  cudaGetDriverEntryPoint("cuTensorMapEncodeTiled", &fnp, cudaEnableDefault, &qr);
  EncodeFn fn = (EncodeFn)fnp;
  void* qptr = nullptr;
  cudaGetSymbolAddress(&qptr, g_QKV);

  CUtensorMap tmQ9, tmQ5, tmN, tmW1, tmW2, tmWo, tmOut, tmX;
  { cuuint64_t d[3] = {64, 576, 27}, s[2] = {3456, 128}; cuuint32_t b[3] = {64, 16, 5}; make_map(fn, &tmQ5, wqkv, 3, d, s, b, CU_TENSOR_MAP_SWIZZLE_128B); }
  { cuuint64_t d[3] = {64, 576, 27}, s[2] = {3456, 128}; cuuint32_t b[3] = {64, 16, 9}; make_map(fn, &tmQ9, wqkv, 3, d, s, b, CU_TENSOR_MAP_SWIZZLE_128B); }
  { cuuint64_t d[2] = {1536, 3072}, s[1] = {3072}; cuuint32_t b[2] = {8, 32}; make_map(fn, &tmN, qptr, 2, d, s, b, CU_TENSOR_MAP_SWIZZLE_NONE); }
  { cuuint64_t d[3] = {64, 576, 72}, s[2] = {9216, 128}; cuuint32_t b[3] = {64, 64, 2}; make_map(fn, &tmW1, w1, 3, d, s, b, CU_TENSOR_MAP_SWIZZLE_128B); }
  { cuuint64_t d[3] = {64, 4608, 9}, s[2] = {1152, 128}; cuuint32_t b[3] = {64, 16, 9}; make_map(fn, &tmW2, w2, 3, d, s, b, CU_TENSOR_MAP_SWIZZLE_128B); }
  { cuuint64_t d[3] = {64, 576, 9}, s[2] = {1152, 128}; cuuint32_t b[3] = {64, 48, 5}; make_map(fn, &tmWo, wo, 3, d, s, b, CU_TENSOR_MAP_SWIZZLE_128B); }

  { cuuint64_t d[2] = {576, 2048}, s[1] = {1152}; cuuint32_t b[2] = {64, 16}; make_map(fn, &tmOut, d_out, 2, d, s, b, CU_TENSOR_MAP_SWIZZLE_128B); }

  { cuuint64_t d[3] = {64, 2048, 9}, s[2] = {1152, 128}; cuuint32_t b[3] = {64, 64, 5}; make_map(fn, &tmX, x, 3, d, s, b, CU_TENSOR_MAP_SWIZZLE_128B); }
  cudaFuncSetAttribute(fused_kernel, cudaFuncAttributeMaxDynamicSharedMemorySize, SMEM_BYTES);
  fused_kernel<<<132, NTHREADS, SMEM_BYTES, cudaStreamPerThread>>>(tmQ9, tmQ5, tmN, tmW1, tmW2, tmWo, tmOut, tmX, x, b1, b2, wqkv,
                                                                   0xBF00BF00u, 0x00030003u);
}
```
